```python
import torch

def _softmax(x, axis=-1):
    return torch.softmax(x, dim=axis)
def _gelu(x):
    return torch.nn.functional.gelu(x, approximate="tanh")
def _silu(x):
    return torch.nn.functional.silu(x)
def _sigmoid(x):
    return torch.sigmoid(x)
def _layernorm(x, axis=-1, eps=1e-5):
    m = x.mean(dim=axis, keepdim=True)
    v = x.var(dim=axis, keepdim=True, unbiased=False)
    return (x - m) / torch.sqrt(v + eps)
def _scatter_add(tgt, idx, src, axis=0):
    return tgt.clone().index_add_(axis, idx, src)
def _segment_sum(src, seg, n):
    out = torch.zeros((n,) + src.shape[1:], dtype=src.dtype)
    return out.index_add_(0, seg, src)
def _pad(x, pw):
    flat = tuple(v for pair in reversed(pw) for v in pair)
    return torch.nn.functional.pad(x, flat)

kernel_name = 'sequential_preLN__compressed_kv_cla__glu_gated_geglu__decode'

def setup_inputs():

    _w = (lambda a: (lambda t: t.to(torch.bfloat16) if t.is_floating_point() else t)(torch.as_tensor(a)))
    def _A_setup():
        B, H, Sq, Sk, D, M = 1, 32, 1, 8192, 128, 640
        Dc = 4 * D
        return {
            "x": _w((lambda *s: torch.randn(*s, dtype=torch.bfloat16) * 0.05)(B, Sq, M)),
            "c_kv": _w((lambda *s: torch.randn(*s, dtype=torch.bfloat16) * 0.8)(B, Sk, Dc)),
            "w_q": _w((lambda *s: torch.randn(*s, dtype=torch.bfloat16) * 1.6)(M, H, D) * (M ** -0.5)),
            "w_uk": _w((lambda *s: torch.randn(*s, dtype=torch.bfloat16) * 1.6)(Dc, H, D) * (Dc ** -0.5)),
            "w_uv": _w((lambda *s: torch.randn(*s, dtype=torch.bfloat16) * 0.8)(Dc, H, D) * (Dc ** -0.5)),
            "w_o": _w((lambda *s: torch.randn(*s, dtype=torch.bfloat16) * 0.8)(H, D, M) * ((H * D) ** -0.5)),
        }
    _A_in = _A_setup()

    def _B_setup():
        B, S, Dm, Df = 1, 1, 640, 1728
        return {
            "x": _w((lambda *s: torch.randn(*s, dtype=torch.bfloat16) * 0.05)(B, S, Dm)),
            "w_gate": _w((lambda *s: torch.randn(*s, dtype=torch.bfloat16) * 0.4)(Dm, Df) * (Dm ** -0.5)),
            "w_up": _w((lambda *s: torch.randn(*s, dtype=torch.bfloat16) * 0.4)(Dm, Df) * (Dm ** -0.5)),
            "w_down": _w((lambda *s: torch.randn(*s, dtype=torch.bfloat16) * 0.4)(Df, Dm) * (Df ** -0.5)),
        }
    _B_in = _B_setup()

    return {
        "A_x": _A_in["x"],
        "A_c_kv": _A_in["c_kv"],
        "A_w_q": _A_in["w_q"],
        "A_w_uk": _A_in["w_uk"],
        "A_w_uv": _A_in["w_uv"],
        "A_w_o": _A_in["w_o"],
        "B_x": _B_in["x"],
        "B_w_gate": _B_in["w_gate"],
        "B_w_up": _B_in["w_up"],
        "B_w_down": _B_in["w_down"],
    }

def reference(A_x, A_c_kv, A_w_q, A_w_uk, A_w_uv, A_w_o, B_x, B_w_gate, B_w_up, B_w_down):
    def _A_ref(x, c_kv, w_q, w_uk, w_uv, w_o):
        B, Sq, M = x.shape[0], x.shape[1], x.shape[2]
        Sk = c_kv.shape[1]
        H, D = w_q.shape[1], w_q.shape[2]
        q = torch.einsum("bqm,mhd->bhqd", x, w_q)
        k = torch.einsum("bkc,chd->bhkd", c_kv, w_uk)
        v = torch.einsum("bkc,chd->bhkd", c_kv, w_uv)
        scores = torch.einsum("bhqd,bhkd->bhqk", q, k) * (D ** -0.5)
        off = Sk - Sq
        qi = torch.arange(Sq)[:, None]
        kj = torch.arange(Sk)[None, :]
        cmask = kj <= (qi + off)
        scores = torch.where(cmask[None, None], scores, -1e9)
        p = _softmax(scores, axis=-1)
        ctx = torch.einsum("bhqk,bhkd->bhqd", p, v)
        return torch.einsum("bhqd,hdm->bqm", ctx, w_o)

    def _B_ref(x, w_gate, w_up, w_down):
        g = torch.einsum("bsd,df->bsf", x, w_gate)
        u = torch.einsum("bsd,df->bsf", x, w_up)
        h = _gelu(g) * u
        return torch.einsum("bsf,fd->bsd", h, w_down)

    x = A_x
    h = x + _A_ref(_layernorm(x, axis=-1), A_c_kv, A_w_q, A_w_uk, A_w_uv, A_w_o)
    h2 = h + _B_ref(_layernorm(h, axis=-1), B_w_gate, B_w_up, B_w_down)
    return h2
```

```cpp
#include <cuda_runtime.h>
#include <cuda_bf16.h>
#include <stdint.h>

namespace {

constexpr int M_ = 640, H_ = 32, D_ = 128, DC_ = 512, SK_ = 8192, DF_ = 1728;
constexpr int NSPLIT = 128, ROWS = SK_ / NSPLIT;

__device__ float g_q[H_ * D_];
__device__ float g_qabs[H_ * DC_];
__device__ float g_opart[NSPLIT * H_ * DC_];
__device__ float g_mpart[NSPLIT * H_];
__device__ float g_lpart[NSPLIT * H_];
__device__ float g_ctx[H_ * D_];
__device__ float g_h[M_];
__device__ float g_hmid[DF_];

__device__ __forceinline__ float bfr(float x) { return __bfloat162float(__float2bfloat16(x)); }

__device__ void layernorm_bf16(const float* xin  , float* xn, float* red) {
    int tid = threadIdx.x;
    float s = 0.f;
    for (int i = tid; i < M_; i += blockDim.x) s += xin[i];
    for (int o = 16; o > 0; o >>= 1) s += __shfl_xor_sync(0xffffffffu, s, o);
    if ((tid & 31) == 0) red[tid >> 5] = s;
    __syncthreads();
    float tot = 0.f;
    for (int w = 0; w < (int)(blockDim.x >> 5); w++) tot += red[w];
    float mean = tot / (float)M_;
    __syncthreads();
    float v = 0.f;
    for (int i = tid; i < M_; i += blockDim.x) { float d = xin[i] - mean; v += d * d; }
    for (int o = 16; o > 0; o >>= 1) v += __shfl_xor_sync(0xffffffffu, v, o);
    if ((tid & 31) == 0) red[tid >> 5] = v;
    __syncthreads();
    float vt = 0.f;
    for (int w = 0; w < (int)(blockDim.x >> 5); w++) vt += red[w];
    float var = vt / (float)M_;
    float mean_b = bfr(mean);
    float var_b = bfr(var);
    float den = bfr(sqrtf(bfr(var_b + 1e-5f)));
    for (int i = tid; i < M_; i += blockDim.x) xn[i] = bfr(bfr(xin[i] - mean_b) / den);
    __syncthreads();
}

__global__ void k_q(const __nv_bfloat16* __restrict__ x, const __nv_bfloat16* __restrict__ wq) {
    __shared__ float xs[M_], xn[M_], red[32];
    for (int i = threadIdx.x; i < M_; i += blockDim.x) xs[i] = __bfloat162float(x[i]);
    __syncthreads();
    layernorm_bf16(xs, xn, red);
    int col = blockIdx.x * blockDim.x + threadIdx.x;
    float acc = 0.f;
    for (int m = 0; m < M_; m++) acc += xn[m] * __bfloat162float(wq[(size_t)m * (H_ * D_) + col]);
    g_q[col] = bfr(acc);
}

__global__ void k_qabs(const __nv_bfloat16* __restrict__ wuk) {
    int warp = (blockIdx.x * blockDim.x + threadIdx.x) >> 5, lane = threadIdx.x & 31;
    if (warp >= DC_ * H_) return;
    int c = warp / H_, h = warp % H_;
    const __nv_bfloat16* w = wuk + ((size_t)c * H_ + h) * D_;
    float acc = 0.f;
    for (int d = lane; d < D_; d += 32) acc += __bfloat162float(w[d]) * g_q[h * D_ + d];
    for (int o = 16; o > 0; o >>= 1) acc += __shfl_xor_sync(0xffffffffu, acc, o);
    if (lane == 0) g_qabs[h * DC_ + c] = acc;
}

__global__ void k_attn(const __nv_bfloat16* __restrict__ ckv) {
    __shared__ float qs[H_ * DC_ / 4];
    __shared__ float S[H_][ROWS];
    __shared__ float mloc[H_], lloc[H_];
    int split = blockIdx.x, tid = threadIdx.x, warp = tid >> 5, lane = tid & 31;
    const __nv_bfloat16* C = ckv + (size_t)split * ROWS * DC_;
    const float scale = rsqrtf((float)D_);
    (void)qs;
    for (int r = warp; r < ROWS; r += 8) {
        float cv[16];
        for (int j = 0; j < 16; j++) cv[j] = __bfloat162float(C[(size_t)r * DC_ + lane + 32 * j]);
        for (int h = 0; h < H_; h++) {
            float acc = 0.f;
            for (int j = 0; j < 16; j++) acc += cv[j] * g_qabs[h * DC_ + lane + 32 * j];
            for (int o = 16; o > 0; o >>= 1) acc += __shfl_xor_sync(0xffffffffu, acc, o);
            if (lane == 0) S[h][r] = acc * scale;
        }
    }
    __syncthreads();
    if (tid < H_) {
        float m = -INFINITY;
        for (int r = 0; r < ROWS; r++) m = fmaxf(m, S[tid][r]);
        float l = 0.f;
        for (int r = 0; r < ROWS; r++) { float p = __expf(S[tid][r] - m); S[tid][r] = p; l += p; }
        mloc[tid] = m; lloc[tid] = l;
        g_mpart[split * H_ + tid] = m; g_lpart[split * H_ + tid] = l;
    }
    __syncthreads();
    for (int c = tid; c < DC_; c += blockDim.x) {
        float acc[H_];
        for (int h = 0; h < H_; h++) acc[h] = 0.f;
        for (int r = 0; r < ROWS; r++) {
            float cv = __bfloat162float(C[(size_t)r * DC_ + c]);
            for (int h = 0; h < H_; h++) acc[h] += S[h][r] * cv;
        }
        for (int h = 0; h < H_; h++) g_opart[((size_t)split * H_ + h) * DC_ + c] = acc[h];
    }
}

__global__ void k_ctx(const __nv_bfloat16* __restrict__ wuv) {
    __shared__ float O[DC_];
    __shared__ float alpha[NSPLIT];
    __shared__ float linv;
    int h = blockIdx.x, tid = threadIdx.x;
    if (tid == 0) {
        float m = -INFINITY;
        for (int s = 0; s < NSPLIT; s++) m = fmaxf(m, g_mpart[s * H_ + h]);
        float l = 0.f;
        for (int s = 0; s < NSPLIT; s++) { float a = __expf(g_mpart[s * H_ + h] - m); alpha[s] = a; l += a * g_lpart[s * H_ + h]; }
        linv = 1.f / l;
    }
    __syncthreads();
    for (int c = tid; c < DC_; c += blockDim.x) {
        float acc = 0.f;
        for (int s = 0; s < NSPLIT; s++) acc += alpha[s] * g_opart[((size_t)s * H_ + h) * DC_ + c];
        O[c] = acc * linv;
    }
    __syncthreads();
    int d = tid;
    float acc = 0.f;
    for (int c = 0; c < DC_; c++) acc += O[c] * __bfloat162float(wuv[((size_t)c * H_ + h) * D_ + d]);
    g_ctx[h * D_ + d] = bfr(acc);
}

__global__ void k_out(const __nv_bfloat16* __restrict__ wo, const __nv_bfloat16* __restrict__ x) {
    int m = blockIdx.x * blockDim.x + threadIdx.x;
    if (m >= M_) return;
    float acc = 0.f;
    for (int i = 0; i < H_ * D_; i++) acc += g_ctx[i] * __bfloat162float(wo[(size_t)i * M_ + m]);
    g_h[m] = bfr(__bfloat162float(x[m]) + bfr(acc));
}

__global__ void k_ffn1(const __nv_bfloat16* __restrict__ wg, const __nv_bfloat16* __restrict__ wu) {
    __shared__ float hs[M_], xn[M_], red[32];
    for (int i = threadIdx.x; i < M_; i += blockDim.x) hs[i] = g_h[i];
    __syncthreads();
    layernorm_bf16(hs, xn, red);
    int f = blockIdx.x * blockDim.x + threadIdx.x;
    if (f >= DF_) return;
    float g = 0.f, u = 0.f;
    for (int m = 0; m < M_; m++) {
        g += xn[m] * __bfloat162float(wg[(size_t)m * DF_ + f]);
        u += xn[m] * __bfloat162float(wu[(size_t)m * DF_ + f]);
    }
    g = bfr(g); u = bfr(u);
    float inner = 0.7978845608028654f * (g + 0.044715f * g * g * g);
    float ge = bfr(0.5f * g * (1.f + tanhf(inner)));
    g_hmid[f] = bfr(ge * u);
}

__global__ void k_ffn2(const __nv_bfloat16* __restrict__ wd, __nv_bfloat16* __restrict__ out) {
    int m = blockIdx.x * blockDim.x + threadIdx.x;
    if (m >= M_) return;
    float acc = 0.f;
    for (int f = 0; f < DF_; f++) acc += g_hmid[f] * __bfloat162float(wd[(size_t)f * M_ + m]);
    out[m] = __float2bfloat16(g_h[m] + bfr(acc));
}

}

extern "C" void kernel_launch(void* const* d_in, const int* in_sizes, int n_in, void* d_out, int out_size) {
    const __nv_bfloat16* x = (const __nv_bfloat16*)d_in[0];
    const __nv_bfloat16* ckv = (const __nv_bfloat16*)d_in[1];
    const __nv_bfloat16* wq = (const __nv_bfloat16*)d_in[2];
    const __nv_bfloat16* wuk = (const __nv_bfloat16*)d_in[3];
    const __nv_bfloat16* wuv = (const __nv_bfloat16*)d_in[4];
    const __nv_bfloat16* wo = (const __nv_bfloat16*)d_in[5];
    const __nv_bfloat16* wg = (const __nv_bfloat16*)d_in[7];
    const __nv_bfloat16* wu = (const __nv_bfloat16*)d_in[8];
    const __nv_bfloat16* wd = (const __nv_bfloat16*)d_in[9];
    __nv_bfloat16* out = (__nv_bfloat16*)d_out;
    k_q<<<H_ * D_ / 128, 128>>>(x, wq);
    k_qabs<<<DC_ * H_ * 32 / 256, 256>>>(wuk);
    k_attn<<<NSPLIT, 256>>>(ckv);
    k_ctx<<<H_, 128>>>(wuv);
    k_out<<<5, 128>>>(wo, x);
    k_ffn1<<<(DF_ + 127) / 128, 128>>>(wg, wu);
    k_ffn2<<<5, 128>>>(wd, out);
}
```

```cpp
#include <cuda_runtime.h>
#include <cuda_bf16.h>
#include <cuda.h>
#include <stdint.h>

namespace {

constexpr int M_ = 640, H_ = 32, D_ = 128, DC_ = 512, SK_ = 8192, DF_ = 1728;
constexpr int NCTA = 128;
constexpr int NCW = 8;
constexpr int NCT = NCW * 32;
constexpr int NTHR = NCT + 32;
constexpr int KVR = SK_ / NCTA;
constexpr int CPITCH = 1040;
constexpr int NDCTA = DF_ / 16;
constexpr int NRED = M_ / 16;
#define PF_DEPTH 3

constexpr int OFF_WQ = 0;
constexpr int OFF_WUK = 40960;
constexpr int OFF_SRED = 0;
constexpr int OFF_WG = 0;
constexpr int OFF_WU = 20480;
constexpr int OFF_WD = 40960;
constexpr int OFF_CKV = 73728;
constexpr int OFF_WUV = OFF_CKV + KVR * CPITCH;
constexpr int OFF_WO = OFF_WUV + 32768;
constexpr int OFF_XS = OFF_WO + 40960;
constexpr int OFF_XN = OFF_XS + 2560;
constexpr int OFF_RED = OFF_XN + 2560;
constexpr int OFF_QS = OFF_RED + 4096;
constexpr int OFF_PS = OFF_RED;
constexpr int OFF_OS = OFF_QS + 512;
constexpr int OFF_CTX = OFF_OS + 512;
constexpr int OFF_SMALL = OFF_CTX + 512;
constexpr int OFF_ALPHA = OFF_SMALL + 256;
constexpr int OFF_HS = OFF_ALPHA + 512;
constexpr int OFF_BARS = OFF_HS + 2560;
constexpr int NCHUNK = 34;
constexpr int SMEM_BYTES = OFF_BARS + (NCHUNK + 2) * 8;

constexpr int CH_WQ = 0, CH_WUK = 5, CH_CKV = 9, CH_WUV = 17, CH_WO = 21, CH_GU = 26, CH_WD = 31;

struct __align__(128) SyncLine { unsigned done; unsigned cntX1; unsigned cntX2; unsigned pad[29]; };
__device__ SyncLine g_sync;
__device__ __align__(128) unsigned long long g_xa[H_ * 4 * D_];
__device__ __align__(128) uint4 g_x1[DC_ * H_ * 2 / 16];
__device__ __align__(128) uint4 g_x2[NCTA * H_ * DC_ * 2 / 16];
__device__ __align__(128) float2 g_ml[NCTA * H_];
__device__ __align__(128) unsigned long long g_xc[H_ * 4 * D_];
__device__ __align__(128) unsigned long long g_x3a[NCTA * M_];
__device__ __align__(128) unsigned long long g_x3b[M_];
__device__ __align__(128) unsigned long long g_x4[NDCTA * M_];
#define DBG_T(i) do { } while (0)
#define DBG_C(i) do { } while (0)

constexpr int SPIN_LIMIT = 1 << 22;

__device__ __forceinline__ uint32_t s2u(const void* p) { return (uint32_t)__cvta_generic_to_shared(p); }
__device__ __forceinline__ void mbar_init(uint32_t bar, unsigned cnt) {
    asm volatile("mbarrier.init.shared::cta.b64 [%0], %1;" ::"r"(bar), "r"(cnt) : "memory");
}
__device__ __forceinline__ void mbar_expect_tx(uint32_t bar, unsigned bytes) {
    asm volatile("mbarrier.arrive.expect_tx.shared::cta.b64 _, [%0], %1;" ::"r"(bar), "r"(bytes) : "memory");
}
__device__ __forceinline__ void mbar_arrive(uint32_t bar) {
    asm volatile("mbarrier.arrive.shared::cta.b64 _, [%0];" ::"r"(bar) : "memory");
}
__device__ __forceinline__ bool mbar_try_wait(uint32_t bar, unsigned parity) {
    unsigned ok;
    asm volatile("{\n.reg .pred p;\nmbarrier.test_wait.parity.shared::cta.b64 p, [%1], %2;\nselp.u32 %0, 1, 0, p;\n}"
                 : "=r"(ok) : "r"(bar), "r"(parity) : "memory");
    return ok != 0;
}
__device__ __forceinline__ void mbar_wait(uint32_t bar, unsigned parity) {
    int it = 0;
    while (!mbar_try_wait(bar, parity)) { if (++it > (SPIN_LIMIT << 2)) __trap(); }
}
__device__ __forceinline__ void bulk_g2s(uint32_t dst, const void* src, unsigned bytes, uint32_t bar) {
    asm volatile("cp.async.bulk.shared::cluster.global.mbarrier::complete_tx::bytes [%0], [%1], %2, [%3];"
                 ::"r"(dst), "l"(src), "r"(bytes), "r"(bar) : "memory");
}
__device__ __forceinline__ void tma2d(uint32_t dst, const CUtensorMap* tm, int c0, int c1, uint32_t bar) {
    asm volatile("cp.async.bulk.tensor.2d.shared::cluster.global.mbarrier::complete_tx::bytes [%0], [%1, {%3, %4}], [%2];"
                 ::"r"(dst), "l"(tm), "r"(bar), "r"(c0), "r"(c1) : "memory");
}
__device__ __forceinline__ void prefetch_tmap(const CUtensorMap* tm) {
    asm volatile("prefetch.tensormap [%0];" ::"l"(tm) : "memory");
}
__device__ __forceinline__ void cp_async16(uint32_t dst, const void* src) {
    asm volatile("cp.async.cg.shared.global [%0], [%1], 16;" ::"r"(dst), "l"(src) : "memory");
}
__device__ __forceinline__ void cp_async_mbar_arrive_noinc(uint32_t bar) {
    asm volatile("cp.async.mbarrier.arrive.noinc.shared::cta.b64 [%0];" ::"r"(bar) : "memory");
}
__device__ __forceinline__ unsigned ld_relaxed_u32(const unsigned* p) {
    unsigned v; asm volatile("ld.relaxed.gpu.global.u32 %0, [%1];" : "=r"(v) : "l"(p) : "memory"); return v;
}
__device__ __forceinline__ unsigned ld_acquire_u32(const unsigned* p) {
    unsigned v; asm volatile("ld.acquire.gpu.global.u32 %0, [%1];" : "=r"(v) : "l"(p) : "memory"); return v;
}
__device__ __forceinline__ void red_add_u32(unsigned* p, unsigned v) {
    asm volatile("red.relaxed.gpu.global.add.u32 [%0], %1;" ::"l"(p), "r"(v) : "memory");
}
__device__ __forceinline__ unsigned long long ld_relaxed_u64(const unsigned long long* p) {
    unsigned long long v; asm volatile("ld.relaxed.gpu.global.b64 %0, [%1];" : "=l"(v) : "l"(p) : "memory"); return v;
}
__device__ __forceinline__ void ld_relaxed_v2u64(const unsigned long long* p, unsigned long long& a, unsigned long long& b) {
    asm volatile("ld.relaxed.gpu.global.v2.b64 {%0, %1}, [%2];" : "=l"(a), "=l"(b) : "l"(p) : "memory");
}
__device__ __forceinline__ void st_relaxed_u64(unsigned long long* p, unsigned long long v) {
    asm volatile("st.relaxed.gpu.global.b64 [%0], %1;" ::"l"(p), "l"(v) : "memory");
}
__device__ __forceinline__ void st_relaxed_v2u64(unsigned long long* p, unsigned long long a, unsigned long long b) {
    asm volatile("st.relaxed.gpu.global.v2.b64 [%0], {%1, %2};" ::"l"(p), "l"(a), "l"(b) : "memory");
}
__device__ __forceinline__ uint4 ld_cg_v4(const uint4* p) {
    uint4 v; asm volatile("ld.relaxed.gpu.global.v4.u32 {%0, %1, %2, %3}, [%4];" : "=r"(v.x), "=r"(v.y), "=r"(v.z), "=r"(v.w) : "l"(p) : "memory"); return v;
}
__device__ __forceinline__ float2 ld_cg_f2(const float2* p) {
    float2 v; asm volatile("ld.relaxed.gpu.global.v2.f32 {%0, %1}, [%2];" : "=f"(v.x), "=f"(v.y) : "l"(p) : "memory"); return v;
}
__device__ __forceinline__ unsigned long long ll_pack(float v, unsigned tag) {
    return ((unsigned long long)tag << 32) | (unsigned long long)__float_as_uint(v);
}
__device__ __forceinline__ unsigned ll_tag(unsigned long long w) { return (unsigned)(w >> 32); }
__device__ __forceinline__ float ll_val(unsigned long long w) { return __uint_as_float((unsigned)w); }

__device__ __forceinline__ void bsync() { asm volatile("bar.sync 1, %0;" ::"n"(NCT) : "memory"); }
__device__ __forceinline__ void bsync_s() { asm volatile("bar.sync 2, 128;" ::: "memory"); }

__device__ __forceinline__ float bfr(float x) { return __bfloat162float(__float2bfloat16(x)); }
__device__ __forceinline__ float bf_lo(uint32_t w) { return __uint_as_float(w << 16); }
__device__ __forceinline__ float bf_hi(uint32_t w) { return __uint_as_float(w & 0xffff0000u); }
__device__ __forceinline__ uint32_t pack_bf16(float lo, float hi) {
    __nv_bfloat162 t = __floats2bfloat162_rn(lo, hi);
    return *reinterpret_cast<uint32_t*>(&t);
}
__device__ __forceinline__ void fma8(float (&acc)[8], const uint4& w, float s) {
    acc[0] = fmaf(s, bf_lo(w.x), acc[0]); acc[1] = fmaf(s, bf_hi(w.x), acc[1]);
    acc[2] = fmaf(s, bf_lo(w.y), acc[2]); acc[3] = fmaf(s, bf_hi(w.y), acc[3]);
    acc[4] = fmaf(s, bf_lo(w.z), acc[4]); acc[5] = fmaf(s, bf_hi(w.z), acc[5]);
    acc[6] = fmaf(s, bf_lo(w.w), acc[6]); acc[7] = fmaf(s, bf_hi(w.w), acc[7]);
}
__device__ __forceinline__ void ldmatrix_x4(uint32_t (&r)[4], uint32_t addr) {
    asm volatile("ldmatrix.sync.aligned.m8n8.x4.shared.b16 {%0,%1,%2,%3}, [%4];"
                 : "=r"(r[0]), "=r"(r[1]), "=r"(r[2]), "=r"(r[3]) : "r"(addr) : "memory");
}
__device__ __forceinline__ void ldmatrix_x4_trans(uint32_t (&r)[4], uint32_t addr) {
    asm volatile("ldmatrix.sync.aligned.m8n8.x4.trans.shared.b16 {%0,%1,%2,%3}, [%4];"
                 : "=r"(r[0]), "=r"(r[1]), "=r"(r[2]), "=r"(r[3]) : "r"(addr) : "memory");
}
__device__ __forceinline__ void mma_bf16(float (&c)[4], uint32_t a0, uint32_t a1, uint32_t a2, uint32_t a3, uint32_t b0, uint32_t b1) {
    asm volatile("mma.sync.aligned.m16n8k16.row.col.f32.bf16.bf16.f32 {%0,%1,%2,%3}, {%4,%5,%6,%7}, {%8,%9}, {%0,%1,%2,%3};"
                 : "+f"(c[0]), "+f"(c[1]), "+f"(c[2]), "+f"(c[3]) : "r"(a0), "r"(a1), "r"(a2), "r"(a3), "r"(b0), "r"(b1));
}

__device__ __forceinline__ float block_sum(float v, float* small, int warp, int lane, int slot) {
    for (int o = 16; o > 0; o >>= 1) v += __shfl_xor_sync(0xffffffffu, v, o);
    if (lane == 0) small[slot * 8 + warp] = v;
    bsync();
    float t = 0.f;
#pragma unroll
    for (int w = 0; w < NCW; w++) t += small[slot * 8 + w];
    return t;
}

__device__ __forceinline__ void layernorm640(const float* xin, float* xn, float* small, int tid, int warp, int lane) {
    float a0 = xin[tid], a1 = xin[tid + 256], a2 = (tid < 128) ? xin[tid + 512] : 0.f;
    float s = a0 + a1 + a2, q = a0 * a0 + a1 * a1 + a2 * a2;
    for (int o = 16; o > 0; o >>= 1) { s += __shfl_xor_sync(0xffffffffu, s, o); q += __shfl_xor_sync(0xffffffffu, q, o); }
    if (lane == 0) { small[warp] = s; small[8 + warp] = q; }
    bsync();
    float ts = 0.f, tq = 0.f;
#pragma unroll
    for (int w = 0; w < NCW; w++) { ts += small[w]; tq += small[8 + w]; }
    const float mean = ts * (1.0f / M_);
    const float var = fmaxf(tq * (1.0f / M_) - mean * mean, 0.f);
    const float mean_b = bfr(mean);
    const float rden = 1.0f / bfr(sqrtf(bfr(bfr(var) + 1e-5f)));
    xn[tid] = bfr(bfr(a0 - mean_b) * rden);
    xn[tid + 256] = bfr(bfr(a1 - mean_b) * rden);
    if (tid < 128) xn[tid + 512] = bfr(bfr(a2 - mean_b) * rden);
    bsync();
}

struct Params {
    const __nv_bfloat16 *x, *ckv, *wo, *wd;
    __nv_bfloat16* out;
};

__device__ __forceinline__ void producer_warp(const Params& p, const CUtensorMap* tm_wq, const CUtensorMap* tm_wuk, const CUtensorMap* tm_wuv,
                                              const CUtensorMap* tm_wg, const CUtensorMap* tm_wu, unsigned char* smem, int b, int lane) {
    const uint32_t sb = s2u(smem);
    const uint32_t bars = sb + OFF_BARS;
    const int h = b >> 2, r = b & 3;
    const int nchunk = (b < NDCTA) ? NCHUNK : CH_GU;
    if (lane != 0) return;
    for (int k = 0; k < nchunk; k++) {
        if (k == CH_GU) mbar_wait(bars + NCHUNK * 8, 0);
        if (k >= PF_DEPTH) {
            mbar_wait(bars + (k - PF_DEPTH) * 8, 0);
        }
        const uint32_t bar = bars + k * 8;
        if (k < CH_WUK) {
            mbar_expect_tx(bar, 8192);
            tma2d(sb + OFF_WQ + (k - CH_WQ) * 8192, tm_wq, h * D_, 160 * r + (k - CH_WQ) * 32, bar);
        } else if (k < CH_CKV) {
            mbar_expect_tx(bar, 8192);
            tma2d(sb + OFF_WUK + (k - CH_WUK) * 8192, tm_wuk, h * D_, 128 * r + (k - CH_WUK) * 32, bar);
        } else if (k < CH_WUV) {
            mbar_expect_tx(bar, 8192);
#pragma unroll
            for (int i = 0; i < 8; i++) {
                int row = (k - CH_CKV) * 8 + i;
                bulk_g2s(sb + OFF_CKV + row * CPITCH, p.ckv + ((size_t)b * KVR + row) * DC_, 1024, bar);
            }
        } else if (k < CH_WO) {
            mbar_expect_tx(bar, 8192);
            tma2d(sb + OFF_WUV + (k - CH_WUV) * 8192, tm_wuv, h * D_, 128 * r + (k - CH_WUV) * 32, bar);
        } else if (k < CH_GU) {
            mbar_expect_tx(bar, 8192);
            bulk_g2s(sb + OFF_WO + (k - CH_WO) * 8192, p.wo + ((size_t)(h * D_ + 32 * r) * M_) + (k - CH_WO) * 4096, 8192, bar);
        } else if (k < CH_WD) {
            mbar_expect_tx(bar, 8192);
            tma2d(sb + OFF_WG + (k - CH_GU) * 4096, tm_wg, b * 16, (k - CH_GU) * 128, bar);
            tma2d(sb + OFF_WU + (k - CH_GU) * 4096, tm_wu, b * 16, (k - CH_GU) * 128, bar);
        } else {
            unsigned bytes = (k == NCHUNK - 1) ? 4096u : 8192u;
            mbar_expect_tx(bar, bytes);
            bulk_g2s(sb + OFF_WD + (k - CH_WD) * 8192, p.wd + ((size_t)b * 16 * M_) + (k - CH_WD) * 4096, bytes, bar);
        }
    }
}

__global__ void __launch_bounds__(NTHR, 1) fused_kernel(const Params p, const __grid_constant__ CUtensorMap tm_wq, const __grid_constant__ CUtensorMap tm_wuk,
                                                        const __grid_constant__ CUtensorMap tm_wuv, const __grid_constant__ CUtensorMap tm_wg,
                                                        const __grid_constant__ CUtensorMap tm_wu) {
    extern __shared__ __align__(1024) unsigned char smem[];
    const int tid = threadIdx.x, warp = tid >> 5, lane = tid & 31;
    const int b = blockIdx.x;
    const uint32_t sb = s2u(smem);
    const uint32_t bars = sb + OFF_BARS;

    float xv0 = 0.f, xv1 = 0.f, xv2 = 0.f;
    unsigned done0 = 0;
    if (tid < NCT) {
        xv0 = __bfloat162float(p.x[tid]);
        xv1 = __bfloat162float(p.x[tid + 256]);
        if (tid < 128) xv2 = __bfloat162float(p.x[tid + 512]);
        if (tid == 0) done0 = ld_relaxed_u32(&g_sync.done);
    }
    if (tid == NCT) {
        prefetch_tmap(&tm_wq); prefetch_tmap(&tm_wuk); prefetch_tmap(&tm_wuv);
        if (b < NDCTA) { prefetch_tmap(&tm_wg); prefetch_tmap(&tm_wu); }
        for (int k = 0; k < NCHUNK; k++) mbar_init(bars + k * 8, 1u);
        mbar_init(bars + NCHUNK * 8, 1);
        asm volatile("fence.mbarrier_init.release.cluster;" ::: "memory");
        asm volatile("fence.proxy.async.shared::cta;" ::: "memory");
    }
    __syncthreads();
    if (warp == NCW) {
        producer_warp(p, &tm_wq, &tm_wuk, &tm_wuv, &tm_wg, &tm_wu, smem, b, lane);
        return;
    }

    float* xs = reinterpret_cast<float*>(smem + OFF_XS);
    float* xn = reinterpret_cast<float*>(smem + OFF_XN);
    float* red = reinterpret_cast<float*>(smem + OFF_RED);
    float* qs = reinterpret_cast<float*>(smem + OFF_QS);
    float* os = reinterpret_cast<float*>(smem + OFF_OS);
    float* ctxs = reinterpret_cast<float*>(smem + OFF_CTX);
    float* small = reinterpret_cast<float*>(smem + OFF_SMALL);
    float* alpha = reinterpret_cast<float*>(smem + OFF_ALPHA);
    float* hs = reinterpret_cast<float*>(smem + OFF_HS);

    const int h = b >> 2, r = b & 3;
    const int o16 = tid & 15, slot = tid >> 4;

    if (tid < 128) { g_xa[b * 128 + tid] = 0ull; g_xc[b * 128 + tid] = 0ull; }
    for (int i = tid; i < M_; i += NCT) g_x3a[b * M_ + i] = 0ull;
    if (b < NDCTA) for (int i = tid; i < M_; i += NCT) g_x4[b * M_ + i] = 0ull;
    if (b < NRED && tid < 16) g_x3b[b * 16 + tid] = 0ull;

    xs[tid] = xv0; xs[tid + 256] = xv1;
    if (tid < 128) xs[tid + 512] = xv2;
    if (tid == 0) reinterpret_cast<unsigned*>(small)[32] = done0;
    bsync();
    const unsigned epoch = reinterpret_cast<unsigned*>(small)[32] / NCTA;
    const unsigned tag = epoch + 1u;
    const unsigned cnt_target = tag * NCTA;

    layernorm640(xs, xn, small, tid, warp, lane);
    DBG_T(0);

    {
        float acc[8] = {0.f, 0.f, 0.f, 0.f, 0.f, 0.f, 0.f, 0.f};
#pragma unroll 1
        for (int ch = 0; ch < 5; ch++) {
            mbar_wait(bars + (CH_WQ + ch) * 8, 0);
#pragma unroll
            for (int i = 0; i < 2; i++) {
                int ml = ch * 32 + i * 16 + slot;
                uint4 w = *reinterpret_cast<const uint4*>(smem + OFF_WQ + ml * 256 + o16 * 16);
                fma8(acc, w, xn[160 * r + ml]);
            }
        }
#pragma unroll
        for (int j = 0; j < 8; j++) acc[j] += __shfl_xor_sync(0xffffffffu, acc[j], 16);
        if (lane < 16) {
            float4* dst = reinterpret_cast<float4*>(red + warp * 128 + o16 * 8);
            dst[0] = make_float4(acc[0], acc[1], acc[2], acc[3]);
            dst[1] = make_float4(acc[4], acc[5], acc[6], acc[7]);
        }
        bsync();
        DBG_C(5);
        if (tid < 128) {
            float s = 0.f;
#pragma unroll
            for (int w = 0; w < NCW; w++) s += red[w * 128 + tid];
            st_relaxed_u64(&g_xa[b * 128 + tid], ll_pack(s, tag));
            const unsigned long long* src = &g_xa[(h * 4) * 128 + tid];
            unsigned long long w0, w1, w2, w3;
            int it = 0;
            do {
                w0 = ld_relaxed_u64(src); w1 = ld_relaxed_u64(src + 128); w2 = ld_relaxed_u64(src + 256); w3 = ld_relaxed_u64(src + 384);
                if (++it > SPIN_LIMIT) __trap();
            } while (ll_tag(w0) != tag || ll_tag(w1) != tag || ll_tag(w2) != tag || ll_tag(w3) != tag);
            float q = bfr(((ll_val(w0) + ll_val(w1)) + ll_val(w2)) + ll_val(w3));
            qs[tid] = q;
        }
        bsync();
    }
    DBG_T(1);
    {
        float qv[8];
#pragma unroll
        for (int j = 0; j < 8; j++) qv[j] = qs[o16 * 8 + j];
        __nv_bfloat16* qa = reinterpret_cast<__nv_bfloat16*>(os);
        const float scale = 0.08838834764831845f;
#pragma unroll 1
        for (int ch = 0; ch < 4; ch++) {
            mbar_wait(bars + (CH_WUK + ch) * 8, 0);
#pragma unroll
            for (int i = 0; i < 2; i++) {
                int cl = ch * 32 + i * 16 + slot;
                uint4 w = *reinterpret_cast<const uint4*>(smem + OFF_WUK + cl * 256 + o16 * 16);
                float a = bf_lo(w.x) * qv[0];
                a = fmaf(bf_hi(w.x), qv[1], a); a = fmaf(bf_lo(w.y), qv[2], a); a = fmaf(bf_hi(w.y), qv[3], a);
                a = fmaf(bf_lo(w.z), qv[4], a); a = fmaf(bf_hi(w.z), qv[5], a);
                a = fmaf(bf_lo(w.w), qv[6], a); a = fmaf(bf_hi(w.w), qv[7], a);
                a += __shfl_xor_sync(0xffffffffu, a, 8);
                a += __shfl_xor_sync(0xffffffffu, a, 4);
                a += __shfl_xor_sync(0xffffffffu, a, 2);
                a += __shfl_xor_sync(0xffffffffu, a, 1);
                if (o16 == 0) qa[cl] = __float2bfloat16(a * scale);
            }
        }
        bsync();
        DBG_C(6);
        if (tid < 16) {
            const int kp = tid >> 2, t = tid & 3;
            const uint32_t* q32 = reinterpret_cast<const uint32_t*>(qa);
            uint4 v;
            v.x = q32[(kp * 32 + 2 * t) >> 1];
            v.y = q32[(kp * 32 + 2 * t + 8) >> 1];
            v.z = q32[(kp * 32 + 16 + 2 * t) >> 1];
            v.w = q32[(kp * 32 + 16 + 2 * t + 8) >> 1];
            const int mt = h >> 4, half = (h >> 3) & 1, g = h & 7;
            g_x1[(((r * 4 + kp) * 2 + mt) * 2 + half) * 32 + g * 4 + t] = v;
            DBG_C(7);
            __threadfence();
            DBG_C(8);
            __syncwarp(0xffffu);
            if (tid == 0) red_add_u32(&g_sync.cntX1, 1u);
        }
    }
    DBG_T(2);

    float* sred = reinterpret_cast<float*>(smem + OFF_SRED);
    if (warp < 4) {
        const int ws = warp;
#pragma unroll 1
        for (int ch = 0; ch < 8; ch++) mbar_wait(bars + (CH_CKV + ch) * 8, 0);
        DBG_C(9);
        if (tid == 0) {
            int it = 0;
            while (ld_acquire_u32(&g_sync.cntX1) < cnt_target) { if (++it > SPIN_LIMIT) __trap(); }
        }
        DBG_C(10);
        bsync_s();
        uint32_t a[4][2][2][4];
#pragma unroll
        for (int kp = 0; kp < 4; kp++)
#pragma unroll
            for (int mt = 0; mt < 2; mt++)
#pragma unroll
                for (int half = 0; half < 2; half++) {
                    uint4 v = ld_cg_v4(&g_x1[(((ws * 4 + kp) * 2 + mt) * 2 + half) * 32 + lane]);
                    a[kp][0][mt][half] = v.x; a[kp][0][mt][2 + half] = v.y;
                    a[kp][1][mt][half] = v.z; a[kp][1][mt][2 + half] = v.w;
                }
        DBG_C(11);
        float acc[2][8][4];
#pragma unroll
        for (int mt = 0; mt < 2; mt++)
#pragma unroll
            for (int nt = 0; nt < 8; nt++)
#pragma unroll
                for (int j = 0; j < 4; j++) acc[mt][nt][j] = 0.f;
#pragma unroll
        for (int kp = 0; kp < 4; kp++) {
#pragma unroll
            for (int nt = 0; nt < 8; nt++) {
                uint32_t bfr4[4];
                ldmatrix_x4(bfr4, sb + OFF_CKV + (nt * 8 + (lane & 7)) * CPITCH + (ws * 128 + kp * 32 + (lane >> 3) * 8) * 2);
#pragma unroll
                for (int mt = 0; mt < 2; mt++) {
                    mma_bf16(acc[mt][nt], a[kp][0][mt][0], a[kp][0][mt][1], a[kp][0][mt][2], a[kp][0][mt][3], bfr4[0], bfr4[1]);
                    mma_bf16(acc[mt][nt], a[kp][1][mt][0], a[kp][1][mt][1], a[kp][1][mt][2], a[kp][1][mt][3], bfr4[2], bfr4[3]);
                }
            }
        }
        DBG_C(12);
        const int g = lane >> 2, t = lane & 3;
#pragma unroll
        for (int mt = 0; mt < 2; mt++)
#pragma unroll
            for (int nt = 0; nt < 8; nt++) {
                float* d0 = sred + (ws * 32 + mt * 16 + g) * 72 + nt * 8 + 2 * t;
                *reinterpret_cast<float2*>(d0) = make_float2(acc[mt][nt][0], acc[mt][nt][1]);
                *reinterpret_cast<float2*>(d0 + 8 * 72) = make_float2(acc[mt][nt][2], acc[mt][nt][3]);
            }
    }
    bsync();
    DBG_T(3);
    __nv_bfloat16* ps = reinterpret_cast<__nv_bfloat16*>(smem + OFF_PS);
    {
        const int hh = tid >> 3, part = tid & 7;
        float s[8];
#pragma unroll
        for (int j = 0; j < 8; j++) s[j] = 0.f;
#pragma unroll
        for (int w = 0; w < 4; w++) {
            const float4* src = reinterpret_cast<const float4*>(sred + (w * 32 + hh) * 72 + part * 8);
            float4 u = src[0], v = src[1];
            s[0] += u.x; s[1] += u.y; s[2] += u.z; s[3] += u.w; s[4] += v.x; s[5] += v.y; s[6] += v.z; s[7] += v.w;
        }
        float m = fmaxf(fmaxf(fmaxf(s[0], s[1]), fmaxf(s[2], s[3])), fmaxf(fmaxf(s[4], s[5]), fmaxf(s[6], s[7])));
        m = fmaxf(m, __shfl_xor_sync(0xffffffffu, m, 1));
        m = fmaxf(m, __shfl_xor_sync(0xffffffffu, m, 2));
        m = fmaxf(m, __shfl_xor_sync(0xffffffffu, m, 4));
        float e[8], l = 0.f;
#pragma unroll
        for (int j = 0; j < 8; j++) { e[j] = __expf(s[j] - m); l += e[j]; }
        l += __shfl_xor_sync(0xffffffffu, l, 1);
        l += __shfl_xor_sync(0xffffffffu, l, 2);
        l += __shfl_xor_sync(0xffffffffu, l, 4);
        uint4 pk;
        pk.x = pack_bf16(e[0], e[1]); pk.y = pack_bf16(e[2], e[3]); pk.z = pack_bf16(e[4], e[5]); pk.w = pack_bf16(e[6], e[7]);
        bsync();
        *reinterpret_cast<uint4*>(ps + hh * 72 + part * 8) = pk;
        if (part == 0) g_ml[b * H_ + hh] = make_float2(m, l);
        if (tid == 0) mbar_arrive(bars + NCHUNK * 8);
    }
    bsync();
    DBG_C(13);
    {
        float acc[2][8][4];
#pragma unroll
        for (int mt = 0; mt < 2; mt++)
#pragma unroll
            for (int nt = 0; nt < 8; nt++)
#pragma unroll
                for (int j = 0; j < 4; j++) acc[mt][nt][j] = 0.f;
        const uint32_t psb = sb + OFF_PS;
#pragma unroll
        for (int ks = 0; ks < 4; ks++) {
            uint32_t af[2][4];
#pragma unroll
            for (int mt = 0; mt < 2; mt++)
                ldmatrix_x4(af[mt], psb + ((mt * 16 + (lane & 7) + ((lane >> 3) & 1) * 8) * 72 + ks * 16 + (lane >> 4) * 8) * 2);
#pragma unroll
            for (int np = 0; np < 4; np++) {
                uint32_t bf4[4];
                ldmatrix_x4_trans(bf4, sb + OFF_CKV + (ks * 16 + (lane & 7) + ((lane >> 3) & 1) * 8) * CPITCH + (warp * 64 + np * 16 + (lane >> 4) * 8) * 2);
#pragma unroll
                for (int mt = 0; mt < 2; mt++) {
                    mma_bf16(acc[mt][2 * np], af[mt][0], af[mt][1], af[mt][2], af[mt][3], bf4[0], bf4[1]);
                    mma_bf16(acc[mt][2 * np + 1], af[mt][0], af[mt][1], af[mt][2], af[mt][3], bf4[2], bf4[3]);
                }
            }
        }
        DBG_C(14);
        const int g = lane >> 2, t = lane & 3;
#pragma unroll
        for (int mt = 0; mt < 2; mt++)
#pragma unroll
            for (int half = 0; half < 2; half++)
#pragma unroll
                for (int nh = 0; nh < 2; nh++) {
                    uint4 v;
                    v.x = pack_bf16(acc[mt][nh * 4 + 0][half * 2], acc[mt][nh * 4 + 0][half * 2 + 1]);
                    v.y = pack_bf16(acc[mt][nh * 4 + 1][half * 2], acc[mt][nh * 4 + 1][half * 2 + 1]);
                    v.z = pack_bf16(acc[mt][nh * 4 + 2][half * 2], acc[mt][nh * 4 + 2][half * 2 + 1]);
                    v.w = pack_bf16(acc[mt][nh * 4 + 3][half * 2], acc[mt][nh * 4 + 3][half * 2 + 1]);
                    const int hh = mt * 16 + half * 8 + g;
                    g_x2[((size_t)(b * H_ + hh) * 64) + (warp * 2 + nh) * 4 + t] = v;
                }
    }
    DBG_C(15);
    bsync();
    if (tid == 0) { __threadfence(); red_add_u32(&g_sync.cntX2, 1u); }
    DBG_C(16);
    DBG_T(4);

    if (tid == 0) {
        int it = 0;
        while (ld_acquire_u32(&g_sync.cntX2) < cnt_target) { if (++it > SPIN_LIMIT) __trap(); }
    }
    bsync();
    DBG_T(5);
    {
        const int pc = tid & 15, sg = tid >> 4;
        uint4 v[8];
#pragma unroll
        for (int i = 0; i < 8; i++) v[i] = ld_cg_v4(&g_x2[((size_t)((sg + 16 * i) * H_ + h) * 64) + r * 16 + pc]);
        float2 mlv = make_float2(-INFINITY, 0.f);
        if (tid < 128) mlv = ld_cg_f2(&g_ml[tid * H_ + h]);
        float m = mlv.x;
        for (int o = 16; o > 0; o >>= 1) m = fmaxf(m, __shfl_xor_sync(0xffffffffu, m, o));
        if (lane == 0 && warp < 4) small[16 + warp] = m;
        bsync();
        DBG_C(17);
        const float mg = fmaxf(fmaxf(small[16], small[17]), fmaxf(small[18], small[19]));
        float al = 0.f, lw = 0.f;
        if (tid < 128) { al = __expf(mlv.x - mg); alpha[tid] = al; lw = al * mlv.y; }
        for (int o = 16; o > 0; o >>= 1) lw += __shfl_xor_sync(0xffffffffu, lw, o);
        if (lane == 0 && warp < 4) small[24 + warp] = lw;
        bsync();
        const float linv = 1.0f / ((small[24] + small[25]) + (small[26] + small[27]));
        float acc[8] = {0.f, 0.f, 0.f, 0.f, 0.f, 0.f, 0.f, 0.f};
#pragma unroll
        for (int i = 0; i < 8; i++) fma8(acc, v[i], alpha[sg + 16 * i]);
#pragma unroll
        for (int j = 0; j < 8; j++) acc[j] += __shfl_xor_sync(0xffffffffu, acc[j], 16);
        if (lane < 16) {
            const int base = (pc >> 3) * 64 + ((pc >> 2) & 1) * 32 + 2 * (pc & 3);
#pragma unroll
            for (int ntl = 0; ntl < 4; ntl++)
                *reinterpret_cast<float2*>(red + warp * 128 + base + ntl * 8) = make_float2(acc[2 * ntl], acc[2 * ntl + 1]);
        }
        bsync();
        if (tid < 128) {
            float s = 0.f;
#pragma unroll
            for (int w = 0; w < NCW; w++) s += red[w * 128 + tid];
            os[tid] = s * linv;
        }
        bsync();
        DBG_C(18);
    }
    {
        float acc[8] = {0.f, 0.f, 0.f, 0.f, 0.f, 0.f, 0.f, 0.f};
#pragma unroll 1
        for (int ch = 0; ch < 4; ch++) {
            mbar_wait(bars + (CH_WUV + ch) * 8, 0);
#pragma unroll
            for (int i = 0; i < 2; i++) {
                int cl = ch * 32 + i * 16 + slot;
                uint4 w = *reinterpret_cast<const uint4*>(smem + OFF_WUV + cl * 256 + o16 * 16);
                fma8(acc, w, os[cl]);
            }
        }
#pragma unroll
        for (int j = 0; j < 8; j++) acc[j] += __shfl_xor_sync(0xffffffffu, acc[j], 16);
        if (lane < 16) {
            float4* dst = reinterpret_cast<float4*>(red + warp * 128 + o16 * 8);
            dst[0] = make_float4(acc[0], acc[1], acc[2], acc[3]);
            dst[1] = make_float4(acc[4], acc[5], acc[6], acc[7]);
        }
        bsync();
        DBG_C(19);
        if (tid < 128) {
            float s = 0.f;
#pragma unroll
            for (int w = 0; w < NCW; w++) s += red[w * 128 + tid];
            st_relaxed_u64(&g_xc[b * 128 + tid], ll_pack(s, tag));
            const unsigned long long* src = &g_xc[(h * 4) * 128 + tid];
            unsigned long long w0, w1, w2, w3;
            int it = 0;
            do {
                w0 = ld_relaxed_u64(src); w1 = ld_relaxed_u64(src + 128); w2 = ld_relaxed_u64(src + 256); w3 = ld_relaxed_u64(src + 384);
                if (++it > SPIN_LIMIT) __trap();
            } while (ll_tag(w0) != tag || ll_tag(w1) != tag || ll_tag(w2) != tag || ll_tag(w3) != tag);
            float c = bfr(((ll_val(w0) + ll_val(w1)) + ll_val(w2)) + ll_val(w3));
            ctxs[tid] = c;
        }
        bsync();
    }
    DBG_T(6);
    {
#pragma unroll 1
        for (int ch = 0; ch < 5; ch++) mbar_wait(bars + (CH_WO + ch) * 8, 0);
        DBG_C(20);
        const uint32_t* wo32 = reinterpret_cast<const uint32_t*>(smem + OFF_WO);
        for (int cp = tid; cp < 320; cp += NCT) {
            float a0 = 0.f, a1 = 0.f;
#pragma unroll
            for (int d = 0; d < 32; d++) {
                uint32_t w = wo32[d * 320 + cp];
                float cv = ctxs[32 * r + d];
                a0 = fmaf(cv, bf_lo(w), a0); a1 = fmaf(cv, bf_hi(w), a1);
            }
            st_relaxed_v2u64(&g_x3a[b * M_ + 2 * cp], ll_pack(a0, tag), ll_pack(a1, tag));
        }
    }
    DBG_T(7);
    if (b < NRED) {
        const int pc = tid & 7, sg = tid >> 3;
        float a0 = 0.f, a1 = 0.f;
        unsigned long long w[4][2];
        int it = 0;
        bool ok;
        do {
            ok = true;
#pragma unroll
            for (int i = 0; i < 4; i++) ld_relaxed_v2u64(&g_x3a[(sg + 32 * i) * M_ + b * 16 + 2 * pc], w[i][0], w[i][1]);
#pragma unroll
            for (int i = 0; i < 4; i++) ok = ok && ll_tag(w[i][0]) == tag && ll_tag(w[i][1]) == tag;
            if (++it > SPIN_LIMIT) __trap();
        } while (!ok);
        DBG_C(21);
#pragma unroll
        for (int i = 0; i < 4; i++) { a0 += ll_val(w[i][0]); a1 += ll_val(w[i][1]); }
        a0 += __shfl_xor_sync(0xffffffffu, a0, 8); a1 += __shfl_xor_sync(0xffffffffu, a1, 8);
        a0 += __shfl_xor_sync(0xffffffffu, a0, 16); a1 += __shfl_xor_sync(0xffffffffu, a1, 16);
        if (lane < 8) { red[warp * 16 + 2 * pc] = a0; red[warp * 16 + 2 * pc + 1] = a1; }
        bsync();
        if (tid < 16) {
            float s = 0.f;
#pragma unroll
            for (int w2 = 0; w2 < NCW; w2++) s += red[w2 * 16 + tid];
            float hv = bfr(xs[b * 16 + tid] + bfr(s));
            st_relaxed_u64(&g_x3b[b * 16 + tid], ll_pack(hv, tag));
        }
    }
    DBG_T(8);
    if (b < NDCTA) {
        {
            unsigned long long w0, w1, w2 = 0, w3 = 0;
            const bool second = tid < 64;
            int it = 0;
            bool ok;
            do {
                ld_relaxed_v2u64(&g_x3b[2 * tid], w0, w1);
                if (second) ld_relaxed_v2u64(&g_x3b[512 + 2 * tid], w2, w3);
                ok = ll_tag(w0) == tag && ll_tag(w1) == tag && (!second || (ll_tag(w2) == tag && ll_tag(w3) == tag));
                if (++it > SPIN_LIMIT) __trap();
            } while (!ok);
            hs[2 * tid] = ll_val(w0); hs[2 * tid + 1] = ll_val(w1);
            if (second) { hs[512 + 2 * tid] = ll_val(w2); hs[512 + 2 * tid + 1] = ll_val(w3); }
        }
        bsync();
        DBG_T(9);
        layernorm640(hs, xn, small, tid, warp, lane);
        DBG_C(22);
        {
            const int half = tid & 1, rs = tid >> 1;
            float ag[8] = {0.f, 0.f, 0.f, 0.f, 0.f, 0.f, 0.f, 0.f}, au[8] = {0.f, 0.f, 0.f, 0.f, 0.f, 0.f, 0.f, 0.f};
#pragma unroll 1
            for (int ch = 0; ch < 5; ch++) {
                mbar_wait(bars + (CH_GU + ch) * 8, 0);
                int row = ch * 128 + rs;
                uint4 wgv = *reinterpret_cast<const uint4*>(smem + OFF_WG + row * 32 + half * 16);
                uint4 wuv = *reinterpret_cast<const uint4*>(smem + OFF_WU + row * 32 + half * 16);
                float xv = xn[row];
                fma8(ag, wgv, xv); fma8(au, wuv, xv);
            }
#pragma unroll
            for (int o = 2; o <= 16; o <<= 1)
#pragma unroll
                for (int j = 0; j < 8; j++) { ag[j] += __shfl_xor_sync(0xffffffffu, ag[j], o); au[j] += __shfl_xor_sync(0xffffffffu, au[j], o); }
            if (lane < 2) {
#pragma unroll
                for (int j = 0; j < 8; j++) { red[warp * 32 + half * 8 + j] = ag[j]; red[warp * 32 + 16 + half * 8 + j] = au[j]; }
            }
            bsync();
            if (tid < 32) {
                float s = 0.f;
#pragma unroll
                for (int w = 0; w < NCW; w++) s += red[w * 32 + tid];
                s = bfr(s);
                float u = __shfl_down_sync(0xffffffffu, s, 16);
                if (tid < 16) {
                    float gg = s;
                    float inner = 0.7978845608028654f * (gg + 0.044715f * gg * gg * gg);
                    float ge = bfr(0.5f * gg * (1.f + tanhf(inner)));
                    float hm = bfr(ge * u);
                    small[40 + tid] = hm;
                }
            }
            bsync();
        }
        DBG_T(10);
        {
#pragma unroll 1
            for (int ch = 0; ch < 3; ch++) mbar_wait(bars + (CH_WD + ch) * 8, 0);
            const uint32_t* wd32 = reinterpret_cast<const uint32_t*>(smem + OFF_WD);
            for (int cp = tid; cp < 320; cp += NCT) {
                float a0 = 0.f, a1 = 0.f;
#pragma unroll
                for (int f = 0; f < 16; f++) {
                    uint32_t w = wd32[f * 320 + cp];
                    float hv = small[40 + f];
                    a0 = fmaf(hv, bf_lo(w), a0); a1 = fmaf(hv, bf_hi(w), a1);
                }
                st_relaxed_v2u64(&g_x4[b * M_ + 2 * cp], ll_pack(a0, tag), ll_pack(a1, tag));
            }
        }
        DBG_T(11);
        if (b < NRED) {
            const int pc = tid & 7, sg = tid >> 3;
            float a0 = 0.f, a1 = 0.f;
            unsigned long long w[4][2];
            int it = 0;
            bool ok;
            do {
                ok = true;
#pragma unroll
                for (int i = 0; i < 4; i++) {
                    if (sg + 32 * i < NDCTA) ld_relaxed_v2u64(&g_x4[(sg + 32 * i) * M_ + b * 16 + 2 * pc], w[i][0], w[i][1]);
                }
#pragma unroll
                for (int i = 0; i < 4; i++)
                    if (sg + 32 * i < NDCTA) ok = ok && ll_tag(w[i][0]) == tag && ll_tag(w[i][1]) == tag;
                if (++it > SPIN_LIMIT) __trap();
            } while (!ok);
#pragma unroll
            for (int i = 0; i < 4; i++)
                if (sg + 32 * i < NDCTA) { a0 += ll_val(w[i][0]); a1 += ll_val(w[i][1]); }
            a0 += __shfl_xor_sync(0xffffffffu, a0, 8); a1 += __shfl_xor_sync(0xffffffffu, a1, 8);
            a0 += __shfl_xor_sync(0xffffffffu, a0, 16); a1 += __shfl_xor_sync(0xffffffffu, a1, 16);
            bsync();
            if (lane < 8) { red[warp * 16 + 2 * pc] = a0; red[warp * 16 + 2 * pc + 1] = a1; }
            bsync();
            if (tid < 16) {
                float s = 0.f;
#pragma unroll
                for (int w2 = 0; w2 < NCW; w2++) s += red[w2 * 16 + tid];
                p.out[b * 16 + tid] = __float2bfloat16(hs[b * 16 + tid] + bfr(s));
            }
        }
        DBG_T(12);
    }
    if (tid == 0) red_add_u32(&g_sync.done, 1u);
}

}

typedef CUresult (*TmapEncodeFn)(CUtensorMap*, CUtensorMapDataType, cuuint32_t, void*, const cuuint64_t*, const cuuint64_t*, const cuuint32_t*,
                                 const cuuint32_t*, CUtensorMapInterleave, CUtensorMapSwizzle, CUtensorMapL2promotion, CUtensorMapFloatOOBfill);

static void make_tmap(TmapEncodeFn enc, CUtensorMap* tm, const void* base, int cols, int rows, int boxw, int boxh) {
    cuuint64_t gdim[2] = {(cuuint64_t)cols, (cuuint64_t)rows};
    cuuint64_t gstr[1] = {(cuuint64_t)cols * 2};
    cuuint32_t box[2] = {(cuuint32_t)boxw, (cuuint32_t)boxh};
    cuuint32_t es[2] = {1, 1};
    enc(tm, CU_TENSOR_MAP_DATA_TYPE_BFLOAT16, 2, const_cast<void*>(base), gdim, gstr, box, es, CU_TENSOR_MAP_INTERLEAVE_NONE,
        CU_TENSOR_MAP_SWIZZLE_NONE, CU_TENSOR_MAP_L2_PROMOTION_NONE, CU_TENSOR_MAP_FLOAT_OOB_FILL_NONE);
}

extern "C" void kernel_launch(void* const* d_in, const int* in_sizes, int n_in, void* d_out, int out_size) {
    Params p;
    p.x = (const __nv_bfloat16*)d_in[0];
    p.ckv = (const __nv_bfloat16*)d_in[1];
    p.wo = (const __nv_bfloat16*)d_in[5];
    p.wd = (const __nv_bfloat16*)d_in[9];
    p.out = (__nv_bfloat16*)d_out;
    static TmapEncodeFn enc = nullptr;
    if (!enc) {
        void* fn = nullptr;
        cudaDriverEntryPointQueryResult qr;
        cudaGetDriverEntryPoint("cuTensorMapEncodeTiled", &fn, cudaEnableDefault, &qr);
        enc = (TmapEncodeFn)fn;
        cudaFuncSetAttribute(fused_kernel, cudaFuncAttributeMaxDynamicSharedMemorySize, SMEM_BYTES);
    }
    CUtensorMap tm_wq, tm_wuk, tm_wuv, tm_wg, tm_wu;
    make_tmap(enc, &tm_wq, d_in[2], H_ * D_, M_, D_, 32);
    make_tmap(enc, &tm_wuk, d_in[3], H_ * D_, DC_, D_, 32);
    make_tmap(enc, &tm_wuv, d_in[4], H_ * D_, DC_, D_, 32);
    make_tmap(enc, &tm_wg, d_in[7], DF_, M_, 16, 128);
    make_tmap(enc, &tm_wu, d_in[8], DF_, M_, 16, 128);
    fused_kernel<<<NCTA, NTHR, SMEM_BYTES>>>(p, tm_wq, tm_wuk, tm_wuv, tm_wg, tm_wu);
}
```
